```python
import torch

def _softmax(x, axis=-1):
    return torch.softmax(x, dim=axis)
def _gelu(x):
    return torch.nn.functional.gelu(x, approximate="tanh")
def _silu(x):
    return torch.nn.functional.silu(x)
def _sigmoid(x):
    return torch.sigmoid(x)
def _layernorm(x, axis=-1, eps=1e-5):
    m = x.mean(dim=axis, keepdim=True)
    v = x.var(dim=axis, keepdim=True, unbiased=False)
    return (x - m) / torch.sqrt(v + eps)
def _scatter_add(tgt, idx, src, axis=0):
    return tgt.clone().index_add_(axis, idx, src)
def _segment_sum(src, seg, n):
    out = torch.zeros((n,) + src.shape[1:], dtype=src.dtype)
    return out.index_add_(0, seg, src)
def _pad(x, pw):
    flat = tuple(v for pair in reversed(pw) for v in pair)
    return torch.nn.functional.pad(x, flat)

kernel_name = 'concat_heads__sliding_block__mha_block__prompt'

def setup_inputs():

    _w = (lambda a: (lambda t: t.to(torch.bfloat16) if t.is_floating_point() else t)(torch.as_tensor(a)))
    def _A_setup():
        B, S, D = 1, 2048, 448
        return {
            "x": _w((lambda *s: torch.randn(*s, dtype=torch.bfloat16) * 0.2)(B, S, D)),
            "wqkv": _w((lambda *s: torch.randn(*s, dtype=torch.bfloat16) * 0.8)(D, 3 * D)),
            "wo": _w((lambda *s: torch.randn(*s, dtype=torch.bfloat16) * 3.2)(D, D)),
        }
    _A_in = _A_setup()

    def _B_setup():
        B, S, D, H = 1, 2048, 448, 16
        return {
            "x": _w((lambda *s: torch.randn(*s, dtype=torch.bfloat16) * 0.2)(B, S, D)),
            "wqkv": _w((lambda *s: torch.randn(*s, dtype=torch.bfloat16) * 0.8)(D, 3 * D)),
            "wo": _w((lambda *s: torch.randn(*s, dtype=torch.bfloat16) * 3.2)(D, D)),
        }
    _B_in = _B_setup()

    return {
        "A_x": _A_in["x"],
        "A_wqkv": _A_in["wqkv"],
        "A_wo": _A_in["wo"],
        "B_x": _B_in["x"],
        "B_wqkv": _B_in["wqkv"],
        "B_wo": _B_in["wo"],
    }

def reference(A_x, A_wqkv, A_wo, B_x, B_wqkv, B_wo):
    def _A_ref(x, wqkv, wo):
        B, S, D = x.shape
        H = 16; Dh = D // H; W = 256
        qkv = (lambda x, *d: x.permute(*d))((x @ wqkv).reshape(B, S, 3, H, Dh), 2, 0, 3, 1, 4)
        q, k, v = qkv[0], qkv[1], qkv[2]
        scores = torch.einsum("bhqd,bhkd->bhqk", q, k) * (Dh ** -0.5)
        idx = torch.arange(S)
        mask = (idx[:, None] - idx[None, :] >= 0) & (idx[:, None] - idx[None, :] < W)
        scores = torch.where(mask[None, None], scores, -1e9)
        p = _softmax(scores, axis=-1)
        o = torch.einsum("bhqk,bhkd->bhqd", p, v)
        return (lambda x, *d: x.permute(*d))(o, 0, 2, 1, 3).reshape(B, S, D) @ wo

    def _B_ref(x, wqkv, wo):
        B, S, D = x.shape
        H = 16
        Dh = D // H
        qkv = (lambda x, *d: x.permute(*d))((x @ wqkv).reshape(B, S, 3, H, Dh), 2, 0, 3, 1, 4)
        q, k, v = qkv[0], qkv[1], qkv[2]
        scores = torch.einsum("bhqd,bhkd->bhqk", q, k) * (Dh ** -0.5)
        p = _softmax(scores, axis=-1)
        o = torch.einsum("bhqk,bhkd->bhqd", p, v)
        return (lambda x, *d: x.permute(*d))(o, 0, 2, 1, 3).reshape(B, S, D) @ wo

    a = _A_ref(A_x, A_wqkv, A_wo)
    b = _B_ref(B_x, B_wqkv, B_wo)
    return torch.concatenate([a, b], axis=-1)
```

```cpp
#include <cuda_runtime.h>
#include <cuda_bf16.h>
#include <cuda.h>
#include <stdint.h>

namespace {

constexpr int SEQ = 2048, DM = 448;
constexpr int NCTA = 128, NTHR = 640;
constexpr int NST = 13;
constexpr int STAGE = 16384;
constexpr int P1_STAGE = 57344;
constexpr int SMEM_DATA = 4 * P1_STAGE;
constexpr int SMEM_BYTES = SMEM_DATA + 512  ;

__device__ __align__(1024) uint4 g_kv[2 * 16 * 32 * 512];
__device__ __align__(1024) uint4 g_q[64 * 1024];
__device__ __align__(1024) uint4 g_part[64 * 2048];
__device__ __align__(1024) uint4 g_o[2 * 32 * 16 * 256];
__device__ __align__(128) uint32_t g_epoch[NCTA * 8];
__device__ __align__(128) uint32_t g_cnt1[NCTA * 32];
__device__ __align__(128) uint32_t g_cnt2[96 * 8];

__device__ __forceinline__ void mbar_init(uint32_t bar, uint32_t cnt) {
    asm volatile("mbarrier.init.shared::cta.b64 [%0], %1;" ::"r"(bar), "r"(cnt) : "memory");
}
__device__ __forceinline__ void mbar_expect_tx(uint32_t bar, uint32_t bytes) {
    asm volatile("mbarrier.arrive.expect_tx.shared::cta.b64 _, [%0], %1;" ::"r"(bar), "r"(bytes) : "memory");
}
__device__ __forceinline__ void mbar_arrive(uint32_t bar) {
    asm volatile("mbarrier.arrive.shared::cta.b64 _, [%0];" ::"r"(bar) : "memory");
}
__device__ __forceinline__ void mbar_arrive_if(uint32_t bar, bool cond) {
    asm volatile("{\n.reg .pred p;\nsetp.ne.u32 p, %1, 0;\n@p mbarrier.arrive.shared::cta.b64 _, [%0];\n}"
                 ::"r"(bar), "r"((uint32_t)cond) : "memory");
}
__device__ __forceinline__ void mbar_wait(uint32_t bar, uint32_t parity) {
    asm volatile(
        "{\n.reg .pred p;\n.reg .u32 n;\n"
        "mbarrier.try_wait.parity.shared::cta.b64 p, [%0], %1;\n"
        "@p bra.uni DONE;\n"
        "mov.u32 n, 0;\n"
        "SPIN:\n"
        "mbarrier.try_wait.parity.shared::cta.b64 p, [%0], %1;\n"
        "@p bra.uni DONE;\n"
        "add.u32 n, n, 1;\n"
        "setp.lt.u32 p, n, 4194304;\n"
        "@p bra.uni SPIN;\n"
        "DONE:\n}"
        ::"r"(bar), "r"(parity) : "memory");
}
__device__ __forceinline__ bool mbar_test(uint32_t bar, uint32_t parity) {
    uint32_t ok;
    asm volatile("{\n.reg .pred p;\nmbarrier.test_wait.parity.shared::cta.b64 p, [%1], %2;\nselp.u32 %0, 1, 0, p;\n}"
                 : "=r"(ok) : "r"(bar), "r"(parity) : "memory");
    return ok != 0;
}
__device__ __forceinline__ void bulk_g2s(uint32_t dst, const void* src, uint32_t bytes, uint32_t bar) {
    asm volatile("cp.async.bulk.shared::cluster.global.mbarrier::complete_tx::bytes [%0], [%1], %2, [%3];"
                 ::"r"(dst), "l"(src), "r"(bytes), "r"(bar) : "memory");
}
__device__ __forceinline__ void bulk_s2g(void* dst, uint32_t src, uint32_t bytes) {
    asm volatile("cp.async.bulk.global.shared::cta.bulk_group [%0], [%1], %2;" ::"l"(dst), "r"(src), "r"(bytes) : "memory");
}
__device__ __forceinline__ void tma2d(uint32_t dst, const CUtensorMap* map, int c0, int c1, uint32_t bar) {
    asm volatile("cp.async.bulk.tensor.2d.shared::cluster.global.mbarrier::complete_tx::bytes [%0], [%1, {%3, %4}], [%2];"
                 ::"r"(dst), "l"(map), "r"(bar), "r"(c0), "r"(c1) : "memory");
}
__device__ __forceinline__ void tma_wo(uint32_t dst, const CUtensorMap* map, int c0, int kc, int cg, uint32_t bar) {
    asm volatile("cp.async.bulk.tensor.5d.shared::cluster.global.mbarrier::complete_tx::bytes [%0], [%1, {%3, %4, %5, %6, %7}], [%2];"
                 ::"r"(dst), "l"(map), "r"(bar), "r"(c0), "r"(-(kc & 4)), "r"(kc >> 2), "r"((kc & 3) * 2), "r"(cg) : "memory");
}
__device__ __forceinline__ uint32_t ld_acquire(const uint32_t* p) {
    uint32_t v;
    asm volatile("ld.acquire.gpu.global.u32 %0, [%1];" : "=r"(v) : "l"(p) : "memory");
    return v;
}
__device__ __forceinline__ void wait_flag(const uint32_t* p, uint32_t target) {
    uint32_t n = 0;
    while ((int)(ld_acquire(p) - target) < 0) {
        if (++n > (1u << 22)) break;
    }
}
__device__ __forceinline__ void fence_async_all() { asm volatile("fence.proxy.async.global;" ::: "memory"); }
__device__ __forceinline__ void fence_async_smem() { asm volatile("fence.proxy.async.shared::cta;" ::: "memory"); }
__device__ __forceinline__ void named_bar(int id, int n) { asm volatile("bar.sync %0, %1;" ::"r"(id), "r"(n) : "memory"); }
__device__ __forceinline__ void wg_fence() { asm volatile("wgmma.fence.sync.aligned;" ::: "memory"); }
__device__ __forceinline__ void wg_commit() { asm volatile("wgmma.commit_group.sync.aligned;" ::: "memory"); }
template <int N> __device__ __forceinline__ void wg_wait() { asm volatile("wgmma.wait_group.sync.aligned %0;" ::"n"(N) : "memory"); }
template <int N> __device__ __forceinline__ void pin(float (&r)[N]) {
#pragma unroll
    for (int i = 0; i < N; i++) asm volatile("" : "+f"(r[i])::"memory");
}
__device__ __forceinline__ uint64_t mkdesc(uint32_t addr, uint32_t lbo, uint32_t sbo, uint64_t swz) {
    return (uint64_t)((addr & 0x3FFFF) >> 4) | ((uint64_t)(lbo >> 4) << 16) | ((uint64_t)(sbo >> 4) << 32) | (swz << 62);
}
__device__ __forceinline__ uint32_t pack_bf16(float lo, float hi) {
    uint32_t r;
    asm("cvt.rn.bf16x2.f32 %0, %1, %2;" : "=r"(r) : "f"(hi), "f"(lo));
    return r;
}
__device__ __forceinline__ float ex2(float x) {
    float y;
    asm("ex2.approx.ftz.f32 %0, %1;" : "=f"(y) : "f"(x));
    return y;
}
__device__ __forceinline__ void stsm4(uint32_t addr, uint32_t r0, uint32_t r1, uint32_t r2, uint32_t r3) {
    asm volatile("stmatrix.sync.aligned.m8n8.x4.shared.b16 [%0], {%1, %2, %3, %4};"
                 ::"r"(addr), "r"(r0), "r"(r1), "r"(r2), "r"(r3) : "memory");
}

__device__ __forceinline__ void mma_qk128_init(float (&d)[64], uint64_t da, uint64_t db) {
    asm volatile(
        "wgmma.mma_async.sync.aligned.m64n128k16.f32.bf16.bf16 {%0, %1, %2, %3, %4, %5, %6, %7, %8, %9, %10, %11, %12, "
        "%13, %14, %15, %16, %17, %18, %19, %20, %21, %22, %23, %24, %25, %26, %27, %28, %29, %30, %31, %32, %33, %34, "
        "%35, %36, %37, %38, %39, %40, %41, %42, %43, %44, %45, %46, %47, %48, %49, %50, %51, %52, %53, %54, %55, %56, "
        "%57, %58, %59, %60, %61, %62, %63}, %64, %65, 0, 1, 1, 0, 0; "
        : "=f"(d[0]), "=f"(d[1]), "=f"(d[2]), "=f"(d[3]), "=f"(d[4]), "=f"(d[5]), "=f"(d[6]), "=f"(d[7]), "=f"(d[8]),
          "=f"(d[9]), "=f"(d[10]), "=f"(d[11]), "=f"(d[12]), "=f"(d[13]), "=f"(d[14]), "=f"(d[15]), "=f"(d[16]),
          "=f"(d[17]), "=f"(d[18]), "=f"(d[19]), "=f"(d[20]), "=f"(d[21]), "=f"(d[22]), "=f"(d[23]), "=f"(d[24]),
          "=f"(d[25]), "=f"(d[26]), "=f"(d[27]), "=f"(d[28]), "=f"(d[29]), "=f"(d[30]), "=f"(d[31]), "=f"(d[32]),
          "=f"(d[33]), "=f"(d[34]), "=f"(d[35]), "=f"(d[36]), "=f"(d[37]), "=f"(d[38]), "=f"(d[39]), "=f"(d[40]),
          "=f"(d[41]), "=f"(d[42]), "=f"(d[43]), "=f"(d[44]), "=f"(d[45]), "=f"(d[46]), "=f"(d[47]), "=f"(d[48]),
          "=f"(d[49]), "=f"(d[50]), "=f"(d[51]), "=f"(d[52]), "=f"(d[53]), "=f"(d[54]), "=f"(d[55]), "=f"(d[56]),
          "=f"(d[57]), "=f"(d[58]), "=f"(d[59]), "=f"(d[60]), "=f"(d[61]), "=f"(d[62]), "=f"(d[63])
        : "l"(da), "l"(db));
}
__device__ __forceinline__ void mma_qk128(float (&d)[64], uint64_t da, uint64_t db) {
    asm volatile(
        "wgmma.mma_async.sync.aligned.m64n128k16.f32.bf16.bf16 {%0, %1, %2, %3, %4, %5, %6, %7, %8, %9, %10, %11, %12, "
        "%13, %14, %15, %16, %17, %18, %19, %20, %21, %22, %23, %24, %25, %26, %27, %28, %29, %30, %31, %32, %33, %34, "
        "%35, %36, %37, %38, %39, %40, %41, %42, %43, %44, %45, %46, %47, %48, %49, %50, %51, %52, %53, %54, %55, %56, "
        "%57, %58, %59, %60, %61, %62, %63}, %64, %65, 1, 1, 1, 0, 0; "
        : "+f"(d[0]), "+f"(d[1]), "+f"(d[2]), "+f"(d[3]), "+f"(d[4]), "+f"(d[5]), "+f"(d[6]), "+f"(d[7]), "+f"(d[8]),
          "+f"(d[9]), "+f"(d[10]), "+f"(d[11]), "+f"(d[12]), "+f"(d[13]), "+f"(d[14]), "+f"(d[15]), "+f"(d[16]),
          "+f"(d[17]), "+f"(d[18]), "+f"(d[19]), "+f"(d[20]), "+f"(d[21]), "+f"(d[22]), "+f"(d[23]), "+f"(d[24]),
          "+f"(d[25]), "+f"(d[26]), "+f"(d[27]), "+f"(d[28]), "+f"(d[29]), "+f"(d[30]), "+f"(d[31]), "+f"(d[32]),
          "+f"(d[33]), "+f"(d[34]), "+f"(d[35]), "+f"(d[36]), "+f"(d[37]), "+f"(d[38]), "+f"(d[39]), "+f"(d[40]),
          "+f"(d[41]), "+f"(d[42]), "+f"(d[43]), "+f"(d[44]), "+f"(d[45]), "+f"(d[46]), "+f"(d[47]), "+f"(d[48]),
          "+f"(d[49]), "+f"(d[50]), "+f"(d[51]), "+f"(d[52]), "+f"(d[53]), "+f"(d[54]), "+f"(d[55]), "+f"(d[56]),
          "+f"(d[57]), "+f"(d[58]), "+f"(d[59]), "+f"(d[60]), "+f"(d[61]), "+f"(d[62]), "+f"(d[63])
        : "l"(da), "l"(db));
}
__device__ __forceinline__ void mma_ss128(float (&d)[64], uint64_t da, uint64_t db) {
    asm volatile(
        "wgmma.mma_async.sync.aligned.m64n128k16.f32.bf16.bf16 {%0, %1, %2, %3, %4, %5, %6, %7, %8, %9, %10, %11, %12, "
        "%13, %14, %15, %16, %17, %18, %19, %20, %21, %22, %23, %24, %25, %26, %27, %28, %29, %30, %31, %32, %33, %34, "
        "%35, %36, %37, %38, %39, %40, %41, %42, %43, %44, %45, %46, %47, %48, %49, %50, %51, %52, %53, %54, %55, %56, "
        "%57, %58, %59, %60, %61, %62, %63}, %64, %65, 1, 1, 1, 0, 1; "
        : "+f"(d[0]), "+f"(d[1]), "+f"(d[2]), "+f"(d[3]), "+f"(d[4]), "+f"(d[5]), "+f"(d[6]), "+f"(d[7]), "+f"(d[8]),
          "+f"(d[9]), "+f"(d[10]), "+f"(d[11]), "+f"(d[12]), "+f"(d[13]), "+f"(d[14]), "+f"(d[15]), "+f"(d[16]),
          "+f"(d[17]), "+f"(d[18]), "+f"(d[19]), "+f"(d[20]), "+f"(d[21]), "+f"(d[22]), "+f"(d[23]), "+f"(d[24]),
          "+f"(d[25]), "+f"(d[26]), "+f"(d[27]), "+f"(d[28]), "+f"(d[29]), "+f"(d[30]), "+f"(d[31]), "+f"(d[32]),
          "+f"(d[33]), "+f"(d[34]), "+f"(d[35]), "+f"(d[36]), "+f"(d[37]), "+f"(d[38]), "+f"(d[39]), "+f"(d[40]),
          "+f"(d[41]), "+f"(d[42]), "+f"(d[43]), "+f"(d[44]), "+f"(d[45]), "+f"(d[46]), "+f"(d[47]), "+f"(d[48]),
          "+f"(d[49]), "+f"(d[50]), "+f"(d[51]), "+f"(d[52]), "+f"(d[53]), "+f"(d[54]), "+f"(d[55]), "+f"(d[56]),
          "+f"(d[57]), "+f"(d[58]), "+f"(d[59]), "+f"(d[60]), "+f"(d[61]), "+f"(d[62]), "+f"(d[63])
        : "l"(da), "l"(db));
}
__device__ __forceinline__ void mma_ss40(float (&d)[20], uint64_t da, uint64_t db) {
    asm volatile(
        "wgmma.mma_async.sync.aligned.m64n40k16.f32.bf16.bf16 {%0, %1, %2, %3, %4, %5, %6, %7, %8, %9, %10, %11, %12, "
        "%13, %14, %15, %16, %17, %18, %19}, %20, %21, 1, 1, 1, 0, 1; "
        : "+f"(d[0]), "+f"(d[1]), "+f"(d[2]), "+f"(d[3]), "+f"(d[4]), "+f"(d[5]), "+f"(d[6]), "+f"(d[7]), "+f"(d[8]),
          "+f"(d[9]), "+f"(d[10]), "+f"(d[11]), "+f"(d[12]), "+f"(d[13]), "+f"(d[14]), "+f"(d[15]), "+f"(d[16]),
          "+f"(d[17]), "+f"(d[18]), "+f"(d[19])
        : "l"(da), "l"(db));
}
__device__ __forceinline__ void mma_ss64_init(float (&d)[32], uint64_t da, uint64_t db) {
    asm volatile(
        "wgmma.mma_async.sync.aligned.m64n64k16.f32.bf16.bf16 {%0, %1, %2, %3, %4, %5, %6, %7, %8, %9, %10, %11, %12, "
        "%13, %14, %15, %16, %17, %18, %19, %20, %21, %22, %23, %24, %25, %26, %27, %28, %29, %30, %31}, %32, %33, 0, "
        "1, 1, 0, 0; "
        : "=f"(d[0]), "=f"(d[1]), "=f"(d[2]), "=f"(d[3]), "=f"(d[4]), "=f"(d[5]), "=f"(d[6]), "=f"(d[7]), "=f"(d[8]),
          "=f"(d[9]), "=f"(d[10]), "=f"(d[11]), "=f"(d[12]), "=f"(d[13]), "=f"(d[14]), "=f"(d[15]), "=f"(d[16]),
          "=f"(d[17]), "=f"(d[18]), "=f"(d[19]), "=f"(d[20]), "=f"(d[21]), "=f"(d[22]), "=f"(d[23]), "=f"(d[24]),
          "=f"(d[25]), "=f"(d[26]), "=f"(d[27]), "=f"(d[28]), "=f"(d[29]), "=f"(d[30]), "=f"(d[31])
        : "l"(da), "l"(db));
}
__device__ __forceinline__ void mma_ss64(float (&d)[32], uint64_t da, uint64_t db) {
    asm volatile(
        "wgmma.mma_async.sync.aligned.m64n64k16.f32.bf16.bf16 {%0, %1, %2, %3, %4, %5, %6, %7, %8, %9, %10, %11, %12, "
        "%13, %14, %15, %16, %17, %18, %19, %20, %21, %22, %23, %24, %25, %26, %27, %28, %29, %30, %31}, %32, %33, 1, "
        "1, 1, 0, 0; "
        : "+f"(d[0]), "+f"(d[1]), "+f"(d[2]), "+f"(d[3]), "+f"(d[4]), "+f"(d[5]), "+f"(d[6]), "+f"(d[7]), "+f"(d[8]),
          "+f"(d[9]), "+f"(d[10]), "+f"(d[11]), "+f"(d[12]), "+f"(d[13]), "+f"(d[14]), "+f"(d[15]), "+f"(d[16]),
          "+f"(d[17]), "+f"(d[18]), "+f"(d[19]), "+f"(d[20]), "+f"(d[21]), "+f"(d[22]), "+f"(d[23]), "+f"(d[24]),
          "+f"(d[25]), "+f"(d[26]), "+f"(d[27]), "+f"(d[28]), "+f"(d[29]), "+f"(d[30]), "+f"(d[31])
        : "l"(da), "l"(db));
}
__device__ __forceinline__ void mma_rs32t(float (&d)[16], uint32_t a0, uint32_t a1, uint32_t a2, uint32_t a3, uint64_t db) {
    asm volatile(
        "wgmma.mma_async.sync.aligned.m64n32k16.f32.bf16.bf16 {%0, %1, %2, %3, %4, %5, %6, %7, %8, %9, %10, %11, %12, "
        "%13, %14, %15}, {%16, %17, %18, %19}, %20, 1, 1, 1, 1; "
        : "+f"(d[0]), "+f"(d[1]), "+f"(d[2]), "+f"(d[3]), "+f"(d[4]), "+f"(d[5]), "+f"(d[6]), "+f"(d[7]), "+f"(d[8]),
          "+f"(d[9]), "+f"(d[10]), "+f"(d[11]), "+f"(d[12]), "+f"(d[13]), "+f"(d[14]), "+f"(d[15])
        : "r"(a0), "r"(a1), "r"(a2), "r"(a3), "l"(db));
}
__device__ __forceinline__ void mma_ss112(float (&d)[56], uint64_t da, uint64_t db) {
    asm volatile(
        "wgmma.mma_async.sync.aligned.m64n112k16.f32.bf16.bf16 {%0, %1, %2, %3, %4, %5, %6, %7, %8, %9, %10, %11, %12, "
        "%13, %14, %15, %16, %17, %18, %19, %20, %21, %22, %23, %24, %25, %26, %27, %28, %29, %30, %31, %32, %33, %34, "
        "%35, %36, %37, %38, %39, %40, %41, %42, %43, %44, %45, %46, %47, %48, %49, %50, %51, %52, %53, %54, %55}, %56, "
        "%57, 1, 1, 1, 0, 1; "
        : "+f"(d[0]), "+f"(d[1]), "+f"(d[2]), "+f"(d[3]), "+f"(d[4]), "+f"(d[5]), "+f"(d[6]), "+f"(d[7]), "+f"(d[8]),
          "+f"(d[9]), "+f"(d[10]), "+f"(d[11]), "+f"(d[12]), "+f"(d[13]), "+f"(d[14]), "+f"(d[15]), "+f"(d[16]),
          "+f"(d[17]), "+f"(d[18]), "+f"(d[19]), "+f"(d[20]), "+f"(d[21]), "+f"(d[22]), "+f"(d[23]), "+f"(d[24]),
          "+f"(d[25]), "+f"(d[26]), "+f"(d[27]), "+f"(d[28]), "+f"(d[29]), "+f"(d[30]), "+f"(d[31]), "+f"(d[32]),
          "+f"(d[33]), "+f"(d[34]), "+f"(d[35]), "+f"(d[36]), "+f"(d[37]), "+f"(d[38]), "+f"(d[39]), "+f"(d[40]),
          "+f"(d[41]), "+f"(d[42]), "+f"(d[43]), "+f"(d[44]), "+f"(d[45]), "+f"(d[46]), "+f"(d[47]), "+f"(d[48]),
          "+f"(d[49]), "+f"(d[50]), "+f"(d[51]), "+f"(d[52]), "+f"(d[53]), "+f"(d[54]), "+f"(d[55])
        : "l"(da), "l"(db));
}


struct ExpConst {
    float scale;
    uint32_t half;
    uint32_t off;
    uint32_t tri;
    int warp2;
};
__device__ __forceinline__ uint32_t ex2_fix(float x0, float x1, const ExpConst& c) {
    float t0, t1;
    uint32_t X;
    asm("fma.rn.f32 %0, %1, %2, 0f00003F35;" : "=f"(t0) : "f"(x0), "f"(c.scale));
    asm("fma.rn.f32 %0, %1, %2, 0f00003F35;" : "=f"(t1) : "f"(x1), "f"(c.scale));
    asm("cvt.pack.sat.s16.s32 %0, %1, %2;" : "=r"(X) : "r"(__float_as_uint(t1)), "r"(__float_as_uint(t0)));
    return X;
}
constexpr float UP = 2361183241434822606848.f, DOWN = 1.f / UP;
constexpr float FIX_BIAS = 16182.f / 128.f;
__device__ __forceinline__ uint32_t ex2_pack(float t0, float t1) {
    uint32_t X;
    asm("{\n.reg .b32 a, b;\nmov.b32 a, %1;\nmov.b32 b, %2;\ncvt.pack.sat.s16.s32 %0, a, b;\n}" : "=r"(X) : "f"(t1), "f"(t0));
    return X;
}
__device__ __forceinline__ uint32_t ex2_fin(uint32_t X, const ExpConst& c) {
    uint32_t r, z;
    asm("lop3.b32 %0, %1, 0x007F007F, %2, 0xEA;" : "=r"(z) : "r"(X), "r"(c.half));
    asm("fma.rn.bf16x2 %0, %1, %2, %3;" : "=r"(r) : "r"(X), "r"(z), "r"(X & 0xFF80FF80u));
    return r;
}

constexpr uint32_t POLY_A = 0x5557u, POLY_B = 0xF555D555u;
constexpr float HEADROOM = 56.f, M_INIT = 60.f;
constexpr uint32_t PAD_LO = 0x1b581f04u, PAD_HI = 0xe5f0u;

__device__ __forceinline__ int tid_now() {
    int t;
    asm volatile("mov.u32 %0, %%tid.x;" : "=r"(t));
    return t;
}
__device__ __forceinline__ int cta_now() {
    int t;
    asm volatile("mov.u32 %0, %%ctaid.x;" : "=r"(t));
    return t;
}
__device__ __forceinline__ int row_minus_col() {
    const int tid = tid_now();
    return ((tid >> 5) & 3) * 16 + ((tid & 31) >> 2) - (tid & 3) * 2;
}
__device__ __forceinline__ void write_pads(uint32_t qb, bool odd, uint32_t off, uint32_t p0, uint32_t p1) {
    const uint32_t a = (off & 0xFFFFu) ^ (odd ? 0u : 0x30u);
    asm volatile("{\n.reg .pred p;\nsetp.ne.u32 p, %3, 0;\n@p st.shared.u32 [%0], %1;\n@p st.shared.u32 [%0 + 512], %2;\n}"
                 ::"r"(qb + a), "r"(p0), "r"(p1), "r"((uint32_t)(((off & 8) != 0) != odd)) : "memory");
}
__device__ __forceinline__ void publish_smem() {
    fence_async_smem();
    __syncwarp();
}
template <int N>
__device__ __forceinline__ bool probe(float (&s)[N], float (&o)[16], uint32_t qb, float& m0, float& m1, bool odd,
                                      bool first, int mask, bool force, uint32_t off) {
    auto imax = [](int m, float x, float y) {
        asm("{\n.reg .b32 a, b;\nmov.b32 a, %1;\nmov.b32 b, %2;\nmax.s32 a, a, b;\nmax.s32 %0, %0, a;\n}" : "+r"(m) : "f"(x), "f"(y));
        return m;
    };
    int ia = 0, ib = 0, ic = 0, id = 0;
#pragma unroll
    for (int i = 0; i < N; i += 8) {
        ia = imax(ia, s[i], s[i + 1]);     ib = imax(ib, s[i + 2], s[i + 3]);
        ic = imax(ic, s[i + 4], s[i + 5]); id = imax(id, s[i + 6], s[i + 7]);
    }
    ia = max(ia, ic); ib = max(ib, id);
    bool hit = __any_sync(0xffffffffu, first ? (force || ia > 16182 + 40 * 128 || ia < 16182 - 75 * 128 || ib > 0x42200000)
                                                   : (ia > 16182 + 128 || ib > 0x3F800000));
    if (first) {
        m0 = m1 = M_INIT;
        hit |= __popc(__ballot_sync(0xffffffffu, ia > 16182 || ib > 0)) >= 10;
    }
    if (__builtin_expect(hit, 0)) {
        if (N == 32 && mask) {
            const int d = row_minus_col();
#pragma unroll
            for (int i = 0; i < 32; i++) {
                const bool le = d + ((i >> 1) & 1) * 8 - 8 * (i >> 2) - (i & 1) >= 0;
                if (le != (mask == 1)) s[i] = -INFINITY;
            }
        }
        float a = fmaxf(s[0], s[1]), b = fmaxf(s[2], s[3]);
#pragma unroll
        for (int i = 4; i < N; i += 4) { a = fmaxf(a, fmaxf(s[i], s[i + 1])); b = fmaxf(b, fmaxf(s[i + 2], s[i + 3])); }
        a = fmaxf(a, __shfl_xor_sync(0xffffffffu, a, 1));
        b = fmaxf(b, __shfl_xor_sync(0xffffffffu, b, 1));
        a = fmaxf(a, __shfl_xor_sync(0xffffffffu, a, 2));
        b = fmaxf(b, __shfl_xor_sync(0xffffffffu, b, 2));
        a = rintf(fmaf(a * UP, UP, HEADROOM - FIX_BIAS) * 128.f) * (1.f / 128.f);
        b += HEADROOM;
        if (!first) { a = fmaxf(a, 0.f); b = fmaxf(b, 0.f); }
        const float n0 = m0 + a, n1 = m1 + b;
        a = n0 - m0; b = n1 - m1;
        m0 = n0; m1 = n1;
        const float sa = first ? 1.f : ex2(-a), sb = first ? 1.f : ex2(-b);
        a = a * DOWN * DOWN;
#pragma unroll
        for (int i = 0; i < N; i++) s[i] -= (i & 2) ? b : a;
#pragma unroll
        for (int i = 0; i < 16; i++) o[i] *= (i & 2) ? sb : sa;
        auto split = [&](float m) {
            const uint32_t h = __float_as_uint(-m), r = __float_as_uint(-m - __uint_as_float(h & 0xFFFF0000u));
            const uint32_t l = __float_as_uint(__uint_as_float(r) - __uint_as_float(r & 0xFFFF0000u));
            return (off & 4) ? l >> 16 : __byte_perm(h, r, 0x7632);
        };
        write_pads(qb, odd, off, split((m0 - FIX_BIAS) * DOWN), split(m1 * UP));
        publish_smem();
        if (N == 64) hit = __any_sync(0xffffffffu, ia > 16182 + 56 * 128 || ib > 0x42600000);
    }
    pin(s);
    return hit;
}

__device__ __forceinline__ uint64_t tile_desc(uint32_t addr) { return 0x8000002000010000ull | (addr >> 4); }
__device__ __forceinline__ void qk_tile(float (&s)[32], uint32_t qb, uint64_t kd) {
    mma_ss64_init(s, tile_desc(qb), kd);
    mma_ss64(s, tile_desc(qb) + 2, kd + 2);
    wg_commit();
}
__device__ __forceinline__ void qk_tile(float (&s)[64], uint32_t qb, uint64_t kd) {
    mma_qk128_init(s, tile_desc(qb), kd);
    mma_qk128(s, tile_desc(qb) + 2, kd + 2);
    wg_commit();
}
template <int H, int N>
__device__ __forceinline__ void exp_tile(const float (&s)[N], uint32_t (&p)[16], const ExpConst& ec) {
#pragma unroll
    for (int j = 0; j < 16; j++) {
        const int i = H * 16 + j;
        if (((N == 64 ? POLY_B : POLY_A) >> i) & 1)
            p[j] = ex2_fin((i & 1) ? ex2_fix(s[2 * i], s[2 * i + 1], ec) : ex2_pack(s[2 * i], s[2 * i + 1]), ec);
        else p[j] = pack_bf16(ex2(s[2 * i]), ex2(s[2 * i + 1]));
    }
}
__device__ __forceinline__ void pv_tile(float (&o)[16], const uint32_t (&p)[16], uint64_t kd) {
#pragma unroll
    for (int k = 0; k < 4; k++) mma_rs32t(o, p[4 * k], p[4 * k + 1], p[4 * k + 2], p[4 * k + 3], kd + 512 + k * 64);
    wg_commit();
}

template <int W, int DIAG>
__device__ __forceinline__ void mask_p(uint32_t (&p)[16], uint32_t tri) {
#pragma unroll
    for (int i = 0; i < 16; i++) {
        const int d = (i >> 1) - (i & 1) - 2 * W;
        if (d == 0) p[i] &= DIAG ? tri : ~tri;
        else if ((d > 0) == (DIAG != 0)) p[i] = 0;
    }
}

struct Params {
    CUtensorMap x[2], wo[2], out;
    const uint8_t* w[2];
    const uint8_t* wob;
    uint64_t pslot[4];
    uint32_t pphase[4];
    uint32_t zero;
    uint4 win[16];
};


__device__ __forceinline__ void signal(uint32_t* cnt) {
    asm volatile("red.release.gpu.global.add.u32 [%0], 1;" ::"l"(cnt) : "memory");
}
__device__ __forceinline__ void bulk_commit() { asm volatile("cp.async.bulk.commit_group;" ::: "memory"); }
__device__ __forceinline__ void bulk_wait() { asm volatile("cp.async.bulk.wait_group 0;" ::: "memory"); }

__device__ __forceinline__ void stage_o(float (&o)[16], bool odd, uint32_t stg, uint32_t off) {
    float l0 = odd ? o[0] : o[12], l1 = odd ? o[2] : o[14];
    l0 = __shfl_sync(0xffffffffu, l0, odd ? 0 : 3, 4);
    l1 = __shfl_sync(0xffffffffu, l1, odd ? 0 : 3, 4);
    const bool haspad = ((off & 8) != 0) != odd;
    float r0, r1;
    asm("rcp.approx.ftz.f32 %0, %1;" : "=f"(r0) : "f"(l0));
    asm("rcp.approx.ftz.f32 %0, %1;" : "=f"(r1) : "f"(l1));
    uint32_t r[8];
#pragma unroll
    for (int c = 0; c < 4; c++) {
        const bool pad = haspad && (odd ? c == 0 : c == 3);
        r[2 * c] = pad ? 0u : pack_bf16(o[4 * c] * r0, o[4 * c + 1] * r0);
        r[2 * c + 1] = pad ? 0u : pack_bf16(o[4 * c + 2] * r1, o[4 * c + 3] * r1);
    }
    stsm4(stg + (off >> 16), r[0], r[1], r[2], r[3]);
    stsm4(stg + ((off >> 16) ^ 0x20), r[4], r[5], r[6], r[7]);
}

__host__ __device__ __forceinline__ int slot_of(int br, int p) {
    const int r = p % NST, x = br ? 9 + r + (r >= 5) : 11 + r + (r >= 10);
    return x >= 14 ? x - 14 : x;
}
__device__ __forceinline__ uint4* kv_block(int b, int h, int blk) { return g_kv + (size_t)((b * 16 + h) * 16 + blk) * 1024; }

__device__ __forceinline__ bool overflowed(const float (&o)[16], bool odd, uint32_t off) {
    const float l0 = odd ? o[0] : o[12], l1 = odd ? o[2] : o[14];
    return __any_sync(0xffffffffu, (((off & 8) != 0) != odd) && !(l0 < 1.2e30f && l1 < 1.2e30f && l0 > 8.3e-25f && l1 > 8.3e-25f));
}
__device__ __forceinline__ void exact_rows(float (&o)[16], float& m0, float& m1, uint32_t q, bool odd, uint32_t off,
                                           const uint4* kv, int k0, int n, int row0) {
    float qf[16];
#pragma unroll
    for (int i = 0; i < 8; i++) {
        uint32_t w;
        asm volatile("ld.shared.u32 %0, [%1];" : "=r"(w) : "r"(q + ((off & 0xFFFFu) ^ ((i >> 1) << 4)) + (i & 1) * 512));
        if ((((off & 8) != 0) != odd) && (i >> 1) == (odd ? 0 : 3)) w = 0;
        qf[2 * i] = __uint_as_float(w << 16) * ((i & 1) ? DOWN : UP);
        qf[2 * i + 1] = __uint_as_float(w & 0xFFFF0000u) * ((i & 1) ? DOWN : UP);
    }
#pragma unroll
    for (int i = 0; i < 16; i++) o[i] = 0.f;
    m0 = m1 = -INFINITY;
    const int row = row0 + ((off >> 6) & 63);
#pragma unroll 1
    for (int key = k0; key < k0 + n; key++) {
        const int kk = key & (SEQ - 1);
        const uint32_t* p = reinterpret_cast<const uint32_t*>(kv) + (kk >> 7) * 4096 + (kk & 127) * 16 + ((off >> 2) & 3);
        float s0 = 0.f, s1 = 0.f, v[8];
#pragma unroll
        for (int c = 0; c < 4; c++) {
            const uint32_t kw = __ldcg(p + ((c ^ ((kk >> 1) & 3)) << 2)), vw = __ldcg(p + 2048 + ((c ^ ((kk >> 1) & 3)) << 2));
            const float ka = __uint_as_float(kw << 16) * UP, kb = __uint_as_float(kw & 0xFFFF0000u) * UP;
            s0 += qf[4 * c] * ka + qf[4 * c + 1] * kb;
            s1 += qf[4 * c + 2] * ka + qf[4 * c + 3] * kb;
            v[2 * c] = __uint_as_float(vw << 16);
            v[2 * c + 1] = __uint_as_float(vw & 0xFFFF0000u);
        }
        s0 += __shfl_xor_sync(0xffffffffu, s0, 1); s1 += __shfl_xor_sync(0xffffffffu, s1, 1);
        s0 += __shfl_xor_sync(0xffffffffu, s0, 2); s1 += __shfl_xor_sync(0xffffffffu, s1, 2);
        const bool ok0 = row0 < 0 || (unsigned)(row - key) < 256u, ok1 = row0 < 0 || (unsigned)(row + 8 - key) < 256u;
        const float n0 = ok0 ? fmaxf(m0, s0) : m0, n1 = ok1 ? fmaxf(m1, s1) : m1;
        const float a0 = ok0 ? ex2(m0 - n0) : 1.f, a1 = ok1 ? ex2(m1 - n1) : 1.f;
        const float p0 = ok0 ? ex2(s0 - n0) : 0.f, p1 = ok1 ? ex2(s1 - n1) : 0.f;
        m0 = n0; m1 = n1;
#pragma unroll
        for (int c = 0; c < 4; c++) {
            o[4 * c] = o[4 * c] * a0 + p0 * v[2 * c];         o[4 * c + 1] = o[4 * c + 1] * a0 + p0 * v[2 * c + 1];
            o[4 * c + 2] = o[4 * c + 2] * a1 + p1 * v[2 * c]; o[4 * c + 3] = o[4 * c + 3] * a1 + p1 * v[2 * c + 1];
        }
    }
}

__global__ void __launch_bounds__(NTHR, 1) fused_kernel(const __grid_constant__ Params P) {
    extern __shared__ __align__(1024) uint8_t smem_raw[];
    constexpr uint32_t sb = 1024;
    const uint32_t bars = sb + SMEM_DATA;
    const uint32_t full1 = bars, empty1 = bars + 56, local_ready = bars + 88, pub_done = bars + 96, staged = bars + 104;
    const uint32_t full2 = bars + 144, empty2 = full2 + 8 * 14, qb_raw = empty2 + 8 * 14, kv_out = qb_raw + 8, hi_ready = kv_out + 8, top_ready = hi_ready + 8;
    const int tid = threadIdx.x, lane = tid & 31, warp = (tid >> 5) & 3;
    const int wg = __shfl_sync(0xffffffffu, tid >> 7, 0);
    const int cta = blockIdx.x;
    const int br = cta >> 6, rb = (cta >> 3) & 7, hp = cta & 7;
    const int hole = br ? 0 : 7, item3 = br ? 22 : 25;
    auto copy_w = [&](int kc, int t, const int rows, const int iters) {
        const int c = t % 21, r0 = t / 21;
        const uint8_t* src = P.w[br] + (size_t)(kc * 64 + r0) * (3 * DM * 2) + (c / 7) * (DM * 2) + hp * 112 + (c % 7) * 16;
        const uint32_t dst = sb + (kc & 3) * P1_STAGE + 32768 + (c >> 3) * 8192;
#pragma unroll
        for (int n = 0; n < iters; n++) {
            const int r = r0 + rows * n;
            if (r < 64 && r0 < rows)
                asm volatile("cp.async.cg.shared.global [%0], [%1], 16;"
                             ::"r"(dst + r * 128 + (((c & 7) ^ (r & 7)) << 4)), "l"(src + (size_t)(rows * n) * (3 * DM * 2)) : "memory");
        }
    };
    auto w_done = [&](int kc) {
        asm volatile("cp.async.mbarrier.arrive.noinc.shared::cta.b64 [%0];" ::"r"(full1 + kc * 8) : "memory");
    };
    if (tid == 511) {
#pragma unroll
        for (int kc = 0; kc < 2; kc++) {
            mbar_init(full1 + kc * 8, kc ? 129 : 513);
            asm volatile("fence.mbarrier_init.release.cluster;" ::: "memory");
            mbar_expect_tx(full1 + kc * 8, 32768);
            tma2d(sb + kc * P1_STAGE, &P.x[br], kc * 64, rb * 256, full1 + kc * 8);
        }
    }
    __syncwarp();

    if (wg == 4) {
        asm volatile("setmaxnreg.dec.sync.aligned.u32 32;");
        if (tid == 639) {
#pragma unroll
            for (int i = 2; i < 7; i++) mbar_init(full1 + i * 8, 129);
            asm volatile("fence.mbarrier_init.release.cluster;" ::: "memory");
        } else if (tid == 512) {
#pragma unroll
            for (int i = 0; i < 4; i++) { mbar_init(empty1 + i * 8, 16); mbar_init(staged + i * 8, 4); }
            mbar_init(local_ready, 16); mbar_init(pub_done, 2); mbar_init(kv_out, 1); mbar_init(hi_ready, 8); mbar_init(top_ready, 4);
        } else if (tid == 544) {
#pragma unroll
            for (int i = 0; i < 14; i++) mbar_init(empty2 + i * 8, 16);
        } else if (tid == 576) {
#pragma unroll
            for (int i = 0; i < 14; i++) mbar_init(full2 + i * 8, 1);
            mbar_init(qb_raw, 1);
            asm volatile("fence.mbarrier_init.release.cluster;" ::: "memory");
        }
        named_bar(6, 640);
        mbar_arrive_if(full2 + lane * 8, warp == 2 && lane < 14 && lane != 1 && lane != 12 &&
                                         (lane < 3 || lane > (br ? 8 : 10) || (cta < 8 && lane < 7)));
#pragma unroll 1
        for (int kc = 1; kc < 7; kc++) {
            if (kc >= 4) mbar_wait(empty1 + (kc - 4) * 8, 0);
            if (tid == 639 && kc >= 2) {
                mbar_expect_tx(full1 + kc * 8, 32768);
                tma2d(sb + (kc & 3) * P1_STAGE, &P.x[br], kc * 64, rb * 256, full1 + kc * 8);
            }
            copy_w(kc, tid - 512, 6, 11);
            w_done(kc);
            __syncwarp();
        }
        const uint32_t epoch = *reinterpret_cast<volatile uint32_t*>(&g_epoch[cta * 8]) + 1;
        named_bar(5, 128);
        if ((uint32_t)__cvta_generic_to_shared(smem_raw) != sb) __trap();
        mbar_wait(warp == 1 ? top_ready : local_ready, 0);
        auto load = [&](int p, const uint4* src) {
            const int st = slot_of(br, p);
            if (p >= NST) mbar_wait(empty2 + st * 8, ((p / NST) - 1) & 1);
            mbar_expect_tx(full2 + st * 8, STAGE);
            bulk_g2s(sb + st * STAGE, src, STAGE, full2 + st * 8);
        };
        const int rt3 = cta >> 2;
        if (warp == 0) {
            wait_flag(&g_cnt1[(64 + (lane & 7) * 8 + hp) * 32 + 8], epoch);
            __syncwarp();
            if (lane == 0) {
                fence_async_all();
                if (!br) {
                    mbar_expect_tx(qb_raw, STAGE);
                    bulk_g2s(sb + 7 * STAGE, g_q + (size_t)cta * 1024, STAGE, qb_raw);
                }
                const int p0 = br ? 8 : 10;
#pragma unroll 1
                for (int i = 0; i < 13 + br; i++) {
                    if (p0 + i == NST) mbar_wait(pub_done, 0);
                    const int j = (br || i > 2) ? i : (i == 2 ? 0 : i + 1);
                    if (!br && i == 2) mbar_wait(full2 + 7 * 8, 0);
                    load(p0 + j, kv_block(1, 2 * hp + 1 - br, (2 * rb + 2 + j) & 15));
                }
                if (!br) {
                    wait_flag(&g_cnt1[(64 + cta) * 32 + 16], epoch);
                    fence_async_all();
                    load(23, g_part + (size_t)cta * 2048);
                    load(24, g_part + (size_t)cta * 2048 + 1024);
                }
#pragma unroll 1
                for (int i = 0; i < 8; i++) {
                    if (i == 0 || i == 4 || i == 6) {
                        wait_flag(&g_cnt2[((i ? i * 16 - 32 : 0) + rt3) * 8], epoch * (i ? 8 : 16));
                        fence_async_all();
                    }
                    load(item3 + i * 3 + 1, g_o + (size_t)(((i >> 2) * 32 + rt3) * 4 + (i & 3)) * 1024);
                }
            }
        } else if (warp == 1) {
            if (lane == 0) {
                auto put = [&](int w, int n, bool e) {
                    uint4* dst = kv_block(br, 2 * hp + 1 - e, 2 * rb);
                    const uint32_t src = sb + (e ? 1 : 12) * STAGE;
                    if (n > 1) bulk_s2g(dst, src, STAGE);
                    if (n & 1) {
                        const int o = STAGE + (w & 1) * 4096;
                        bulk_s2g(dst + o / 16, src + o, 4096);
                        bulk_s2g(dst + o / 16 + 512, src + o + 8192, 4096);
                    }
                    if (br && e) bulk_s2g(g_q + (size_t)(cta - 64) * 1024 + w * 256, sb + 11 * STAGE + w * 4096, n * 4096);
                };
                put(3, 1, false); put(3, 1, true);
                mbar_wait(hi_ready, 0);
                put(2, 1, false);
                if (!br) put(2, 1, true);
                const int prev = (cta & 64) | ((cta - 8) & 63), pb = (2 * rb - 1) & 15;
#pragma unroll 1
                for (int g = 0; g < 2; g++) {
                    bulk_commit();
                    bulk_wait();
                    signal(&g_cnt1[cta * 32 + g * 8]);
                    if (g == 0) { mbar_wait(local_ready, 0); put(0, 2, false); }
                    if (cta >= 8 && !(br && g)) {
                        wait_flag(&g_cnt1[prev * 32 + g * 8], epoch);
                        fence_async_all();
                        if (!br) load(7 - g, kv_block(0, 2 * hp, pb - g));
                        load(br ? 7 : 9 - g, kv_block(br, 2 * hp + 1, pb - g));
                    }
                    if (g == 0) put(0, 2 + br, true);
                }
                mbar_arrive(kv_out);
                asm volatile("cp.async.bulk.prefetch.L2.global [%0], %1;" ::"l"(P.wob + cta * 3136), "r"(3136) : "memory");
                asm volatile("prefetch.tensormap [%0];" ::"l"(&P.wo[1]) : "memory");
                asm volatile("prefetch.tensormap [%0];" ::"l"(&P.out) : "memory");
                mbar_arrive(pub_done);
                mbar_wait(pub_done, 0);
#pragma unroll 1
                for (int i = 0; i < 16; i++) {
                    const int p = item3 + (i >> 1) * 3 + (i & 1) * 2, st = slot_of(br, p);
                    mbar_wait(empty2 + st * 8, ((p / NST) - 1) & 1);
                    mbar_expect_tx(full2 + st * 8, STAGE);
                    tma_wo(sb + st * STAGE, &P.wo[i >> 3], 0, i & 7, cta & 3, full2 + st * 8);
                    tma_wo(sb + st * STAGE + 8192, &P.wo[i >> 3], 64, i & 7, cta & 3, full2 + st * 8);
                }
            }
        } else if (warp == 2) {
            if (lane == 0) {
                mbar_arrive(full2 + 8);
                mbar_arrive(full2 + 12 * 8);
#pragma unroll 1
                for (int w = 0; w < 4; w++) {
                    mbar_wait(staged + w * 8, 0);
                    if (br) bulk_s2g(g_part + (size_t)(cta - 64) * 2048 + w * 512, sb + 9 * STAGE + w * 8192, 8192);
                    else {
                        bulk_s2g(g_o + (size_t)((rb * 4 + w) * 16 + hp) * 256, sb + w * 4096, 4096);
                        bulk_s2g(g_o + (size_t)((rb * 4 + 3 - w) * 16 + 8 + hp) * 256, sb + 11 * STAGE + (3 - w) * 4096, 4096);
                    }
                }
                bulk_commit();
                bulk_wait();
                mbar_arrive(pub_done);
                if (br) signal(&g_cnt1[cta * 32 + 16]);
                else {
                    asm volatile("fence.acq_rel.gpu;" ::: "memory");
                    for (int i = 0; i < 4; i++)
                        asm volatile("red.relaxed.gpu.global.add.u32 [%0], 2;" ::"l"(&g_cnt2[(rb * 4 + i) * 8]) : "memory");
                }
                g_epoch[cta * 8] = epoch;
            }
        } else if (!br) {
            mbar_wait(qb_raw, 0);
#pragma unroll
            for (int i = 0; i < 8; i++) {
                const int row = i * 32 + lane;
                asm volatile("st.shared.v2.u32 [%0], {%1, %2};" ::"r"(sb + 7 * STAGE + row * 64 + (((row >> 1) & 3) << 4)),
                             "r"((row & 8) ? PAD_HI : PAD_LO), "r"(0) : "memory");
            }
            fence_async_smem();
            __syncwarp();
            mbar_arrive_if(full2 + 7 * 8, lane == 0);
        }
        return;
    }

    copy_w(0, tid, 24, 3);
    named_bar(6, 640);
    w_done(0);
    asm volatile("setmaxnreg.inc.sync.aligned.u32 112;");
    const bool lane0 = lane == 0;
    {
        float acc1[64], acc2[20];
#pragma unroll
        for (int i = 0; i < 64; i++) acc1[i] = 0.f;
#pragma unroll
        for (int i = 0; i < 20; i++) acc2[i] = 0.f;
        pin(acc1); pin(acc2);
#pragma unroll
        for (int kc = 0; kc < 7; kc++) {
            const uint32_t st = sb + (kc & 3) * P1_STAGE;
            mbar_wait(full1 + kc * 8, 0);
            fence_async_smem();
            if (kc == 5) {
                wg_wait<0>();
                mbar_arrive_if(empty1 + 24, lane0);
                if (wg < 3) named_bar(9 + wg, 256);
            }
            const uint64_t da = mkdesc(st + wg * 8192, 16, 1024, 1), db = mkdesc(st + 32768, 8192, 1024, 1);
            wg_fence();
#pragma unroll
            for (int k = 0; k < 4; k++) {
                mma_ss128(acc1, da + k * 2, db + k * 128);
                mma_ss40(acc2, da + k * 2, db + 1024 + k * 128);
            }
            wg_commit();
            if (kc == 6 && wg) asm volatile("bar.arrive %0, 256;" ::"r"(8 + wg) : "memory");
            if (kc >= 1 && kc <= 3) {
                wg_wait<1>();
                mbar_arrive_if(empty1 + (kc - 1) * 8, lane0);
            }
        }
        wg_wait<0>();
        pin(acc1); pin(acc2);
        auto acc = [&](int i) { return i < 64 ? acc1[i < 64 ? i : 0] : acc2[i < 64 ? 0 : i - 64]; };
        mbar_wait(empty1 + 24, 0);
        const float qscale = 0.18898223650461362f * 1.4426950408889634f;
        const int srow = warp * 16 + (lane & 15);
        const uint32_t sw = (srow >> 1) & 3, ch = lane >> 4;
#pragma unroll
        for (int t = 0; t < 3; t++) {
            const float sc = t == 0 ? qscale * DOWN : (t == 1 ? DOWN : 1.f), sd = t == 0 ? qscale * UP : sc;
            const uint32_t padv = t == 0 ? ((lane & 1) ? 0u : PAD_LO) : (t == 1 ? 0x1C001C00u : 0x3F803F80u);
            const uint32_t padw = t == 0 ? ((lane & 1) ? 0u : PAD_HI) : padv;
            uint32_t r[14];
#pragma unroll
            for (int j = 0; j < 7; j++) {
                r[2 * j] = pack_bf16(acc((t * 7 + j) * 4) * sc, acc((t * 7 + j) * 4 + 1) * sc);
                r[2 * j + 1] = pack_bf16(acc((t * 7 + j) * 4 + 2) * sd, acc((t * 7 + j) * 4 + 3) * sd);
            }
            const uint32_t ra = sb + srow * 64 + (t == 0 ? wg * 4096 : STAGE + (wg >> 1) * STAGE + (wg & 1) * 4096 + (t - 1) * 8192);
            stsm4(ra + ((ch ^ sw) << 4), r[0], r[1], r[2], r[3]);
            stsm4(ra + (((2 + ch) ^ sw) << 4), r[4], r[5], (lane & 2) ? padv : r[6], (lane & 2) ? padw : r[7]);
            stsm4(ra + 11 * STAGE + ((ch ^ sw) << 4), (lane & 2) ? r[6] : padv, (lane & 2) ? r[7] : padw, r[8], r[9]);
            stsm4(ra + 11 * STAGE + (((2 + ch) ^ sw) << 4), r[10], r[11], r[12], r[13]);
        }
        fence_async_smem();
        __syncwarp();
        mbar_arrive_if(lane ? hi_ready + (lane - 1) * 8 : local_ready, lane < max(wg, 1));
        mbar_wait(hi_ready, 0);
    }

    {
        float o[16], m0, m1;
        ExpConst ec;
        ec.scale = __uint_as_float(0x80u + (P.zero & tid));
        ec.half = 0x3F003F00u + (P.zero & tid);
        {
            const int r1 = warp * 16 + (lane >> 2), r2 = warp * 16 + (lane & 15);
            ec.off = (r1 * 64 + (((r1 >> 1) & 3) << 4) + (lane & 3) * 4) | (r2 * 64 + (((lane >> 4) ^ ((r2 >> 1) & 3)) << 4)) << 16;
        }
        {
            const int x = (lane >> 2) - (lane & 3) * 2;
            ec.tri = x > 0 ? 0xFFFFFFFFu : (x == 0 ? 0xFFFFu : 0u);
            ec.warp2 = __shfl_sync(0xffffffffu, warp * 2, 0);
        }
        asm volatile("" : "+f"(ec.scale), "+r"(ec.half), "+r"(ec.off), "+r"(ec.tri));

        if (!br) {
            const uint4* win = P.win + (rb ? 0 : 8) + wg * 2;
            auto tdesc = [&](int t) { return tile_desc(sb) + (uint32_t)((t * 2 - (t & 1)) * 256); };
            float s[32];
            wg_fence();
            qk_tile(s, win[0].x, tdesc(win[0].z & 31));
            wg_wait<0>();
            pin(s);
#pragma unroll 1
            for (int task = 0; task < 2; task++) {
                const bool odd = (wg < 2) != task;
                const uint4 c = win[task];
                const uint32_t q = c.x, qn = c.y;
                const int nt = c.w;
                uint64_t kd = tdesc(c.z & 31);
                uint32_t seq = c.z >> 5;
#pragma unroll
                for (int i = 0; i < 16; i++) o[i] = 0.f;
                const bool chk = probe(s, o, q, m0, m1, odd, true, 1, nt == 1, ec.off);
                int t = 1;
#pragma unroll 1
                do {
                    const int tn = seq & 31, mask = t == 1 ? 1 : (t == 5 ? 2 : 0);
                    const uint64_t kn = tdesc(tn);
                    seq >>= 5;
                    const bool ok = mbar_test(full2 + (tn >> 1) * 8, 0);
                    float e0 = ex2(s[6]), e1 = ex2(s[7]), e2 = ex2(s[10]), e3 = ex2(s[11]);
                    asm volatile("" : "+f"(e0), "+f"(e1), "+f"(e2), "+f"(e3));
                    mbar_wait(hi_ready, 0);
                    wg_wait<0>();
                    pin(o);
                    if (__builtin_expect(chk, 0)) {
                        probe(s, o, q, m0, m1, odd, false, mask, false, ec.off);
                        e0 = ex2(s[6]); e1 = ex2(s[7]); e2 = ex2(s[10]); e3 = ex2(s[11]);
                    }
                    uint32_t p[16];
                    exp_tile<0>(s, p, ec);
                    p[3] = pack_bf16(e0, e1);
                    p[5] = pack_bf16(e2, e3);
                    if (mask) {
                        switch (mask + ec.warp2) {
                            case 1: mask_p<0, 1>(p, ec.tri); break;
                            case 2: mask_p<0, 0>(p, ec.tri); break;
                            case 3: mask_p<1, 1>(p, ec.tri); break;
                            case 4: mask_p<1, 0>(p, ec.tri); break;
                            case 5: mask_p<2, 1>(p, ec.tri); break;
                            case 6: mask_p<2, 0>(p, ec.tri); break;
                            case 7: mask_p<3, 1>(p, ec.tri); break;
                            default: mask_p<3, 0>(p, ec.tri); break;
                        }
                    }
                    if (__builtin_expect(__any_sync(0xffffffffu, !ok), 0)) mbar_wait(full2 + (tn >> 1) * 8, 0);
                    wg_fence();
                    qk_tile(s, t < nt ? q : qn, kn);
                    pv_tile(o, p, kd);
                    wg_wait<1>();
                    pin(s);
                    kd = kn;
                } while (++t <= nt);
                wg_wait<0>();
                pin(o);
                if (__builtin_expect(overflowed(o, odd, ec.off), 0)) {
                    const int row0 = rb * 256 + (odd ? 3 - wg : wg) * 64, k0 = max(row0 + ec.warp2 * 8 - 255, 0);
                    mbar_wait(kv_out, 0);
                    exact_rows(o, m0, m1, q, odd, ec.off, kv_block(0, 2 * hp + odd, 0), k0, row0 + ec.warp2 * 8 + 16 - k0, row0);
                }
                if (!task) stage_o(o, odd, q, ec.off);
            }
        }

        uint64_t seq = br ? 0x3CDull : 0x6543210DCBA98ull;
        int ns = br ? 3 : 13, flip = br ? 99 : 3;
        bool odd = true;
        float s[64];
        mbar_wait(full2 + (br ? 13 : 8) * 8, 0);
        wg_fence();
        qk_tile(s, sb + (br ? 11 : 7) * STAGE + wg * 4096, tile_desc(sb + (br ? 13 : 8) * STAGE));
        if (!br) {
            const int lane = tid_now() & 31;
            mbar_arrive_if(empty2 + (lane < 7 ? lane : lane + 4) * 8, lane < 10);
            stage_o(o, wg >= 2, P.win[wg * 2 + 1].x, ec.off);
            publish_smem();
            mbar_arrive_if(staged + wg * 8, lane0);
        }
#pragma unroll 1
        for (;;) {
            const bool seg = ns != 3;
            const uint32_t q = sb + (seg ? hole : 11) * STAGE + wg * 4096;
            int st = (int)seq & 15;
            uint64_t kd = tile_desc(sb) + (uint32_t)(st * 1024);
            wg_wait<0>();
            pin(s);
#pragma unroll
            for (int i = 0; i < 16; i++) o[i] = 0.f;
            bool chk = true;
#pragma unroll 1
            for (int i = 1;; i++) {
                if (__builtin_expect(chk, 0)) chk = probe(s, o, q, m0, m1, odd, i == 1, 0, false, ec.off) || i > 1;
                seq >>= 4;
                const int sn = (int)seq & 15;
                const uint64_t kn = tile_desc(sb) + (uint32_t)(sn * 1024);
                uint32_t p[16], p2[16];
                exp_tile<0>(s, p, ec);
                wg_fence();
                pv_tile(o, p, kd);
                exp_tile<1>(s, p2, ec);
                wg_fence();
                pv_tile(o, p2, kd + 256);
                if (i == ns) break;
                mbar_wait(full2 + sn * 8, i >= flip);
                wg_wait<0>();
                wg_fence();
                qk_tile(s, q, kn);
                mbar_arrive_if(empty2 + st * 8, lane0);
                st = sn;
                kd = kn;
                wg_wait<0>();
                pin(s); pin(o);
            }
            wg_wait<0>();
            pin(o);
            mbar_arrive_if(empty2 + st * 8, lane0);
            if (__builtin_expect(overflowed(o, odd, ec.off), 0)) {
                mbar_wait(kv_out, 0);
                exact_rows(o, m0, m1, q, odd, ec.off, kv_block(1, 2 * hp + odd, 0), rb * 256 + (br ? SEQ - 128 : 256), ns * 128, -1);
            }
            if (seg) break;
            wg_fence();
            qk_tile(s, sb + wg * 4096, tile_desc(sb + STAGE));
            const int tid = tid_now();
            const uint32_t stg = sb + 9 * STAGE + (tid >> 7) * 8192 + (tid & 127) * 16;
            asm volatile("st.shared.v4.f32 [%0], {%1, %2, %3, %4};" ::"r"(stg), "f"(o[0]), "f"((tid & 2) ? o[1] : m0),
                         "f"(o[2]), "f"((tid & 2) ? o[3] : m1) : "memory");
#pragma unroll
            for (int c = 1; c < 4; c++)
                asm volatile("st.shared.v4.f32 [%0], {%1, %2, %3, %4};" ::"r"(stg + c * 2048),
                             "f"(o[4 * c]), "f"(o[4 * c + 1]), "f"(o[4 * c + 2]), "f"(o[4 * c + 3]) : "memory");
            publish_smem();
            mbar_arrive_if((tid & 31) == 3 ? staged + wg * 8 : empty2 + (9 + (tid & 31)) * 8, (tid & 31) < 4);
            odd = false;
            seq = 0x4321DCBA98765421ull; ns = 16; flip = 7;
        }
        {
            const int tid = tid_now(), cta = cta_now();
            if (!br) {
                float r[16];
                const int s0 = slot_of(0, 23), s1 = slot_of(0, 24);
                mbar_wait(full2 + s0 * 8, 1);
                mbar_wait(full2 + s1 * 8, 1);
#pragma unroll
                for (int c = 0; c < 4; c++)
                    asm volatile("ld.shared.v4.f32 {%0, %1, %2, %3}, [%4];"
                                 : "=f"(r[4 * c]), "=f"(r[4 * c + 1]), "=f"(r[4 * c + 2]), "=f"(r[4 * c + 3])
                                 : "r"(sb + s0 * STAGE + wg * 8192 + c * 2048 + (tid & 127) * 16) : "memory");
                const float n0 = __shfl_sync(0xffffffffu, r[1], tid & 28), n1 = __shfl_sync(0xffffffffu, r[3], tid & 28);
                if (__builtin_expect(__any_sync(0xffffffffu, m0 != n0 || m1 != n1), 0)) {
                    const float f0 = ex2(-0.5f * fabsf(m0 - n0)), f1 = ex2(-0.5f * fabsf(m1 - n1));
#pragma unroll
                    for (int i = 0; i < 16; i++) {
                        const float f = (i & 2) ? f1 : f0;
                        if ((i & 2) ? m1 < n1 : m0 < n0) o[i] = (o[i] * f) * f; else r[i] = (r[i] * f) * f;
                    }
                }
#pragma unroll
                for (int i = 0; i < 16; i++) o[i] += r[i];
            }
            const int tile64 = ((cta >> 3) & 7) * 4 + wg;
            const uint32_t stg = sb + hole * STAGE + wg * 4096;
            stage_o(o, odd, stg, ec.off);
            uint32_t* cnt = &g_cnt2[(32 + odd * 32 + tile64) * 8];
            __syncwarp();
            mbar_arrive_if(empty2 + (slot_of(0, 23) + (tid & 1)) * 8, !br && (tid & 31) < 2);
            uint4* dst = g_o + (size_t)((32 + tile64) * 16 + odd * 8 + (cta & 7)) * 256 + (tid & 96) * 2 + (tid & 31);
#pragma unroll
            for (int i = 0; i < 2; i++) {
                uint4 v;
                asm volatile("ld.shared.v4.u32 {%0, %1, %2, %3}, [%4];" : "=r"(v.x), "=r"(v.y), "=r"(v.z), "=r"(v.w)
                             : "r"(stg + (tid & 96) * 32 + (tid & 31) * 16 + i * 512) : "memory");
                dst[i * 32] = v;
            }
            named_bar(1 + wg, 128);
            if ((tid & 127) == 0) signal(cnt);
            __syncwarp();
        }
    }

    if (wg >= 2) {
        const int tid = tid_now(), cta = cta_now(), lane = tid & 31, warp = (tid >> 5) & 3;
        const bool isb = wg == 2;
        float acc[56];
#pragma unroll
        for (int i = 0; i < 56; i++) acc[i] = 0.f;
        uint64_t sl = P.pslot[br * 2 + isb];
        uint32_t ph = P.pphase[br * 2 + isb];
        int rel0 = 0, so = 0;
        pin(acc);
#pragma unroll 1
        for (int kp = 0; kp < 4; kp++) {
            const int w0 = (int)sl & 15, w1 = (int)(sl >> 8) & 15, rel1 = so;
            so = (int)(sl >> 4) & 15;
            const uint64_t da = mkdesc(sb + so * STAGE, 16, 512, 2);
            const uint64_t db0 = mkdesc(sb + w0 * STAGE, 8192, 1024, 1), db1 = mkdesc(sb + w1 * STAGE, 8192, 1024, 1);
            mbar_wait(full2 + w0 * 8, ph & 1);
            mbar_wait(full2 + so * 8, (ph >> 1) & 1);
            wg_fence();
#pragma unroll
            for (int k = 0; k < 4; k++) mma_ss112(acc, da + (k >> 1) * 256 + (k & 1) * 2, db0 + k * 128);
            wg_commit();
            wg_wait<1>();
            mbar_arrive_if(empty2 + ((lane & 4) ? rel0 : rel1) * 8, !isb && kp && lane < 8);
            mbar_wait(full2 + w1 * 8, (ph >> 2) & 1);
            wg_fence();
#pragma unroll
            for (int k = 0; k < 4; k++) mma_ss112(acc, da + 512 + (k >> 1) * 256 + (k & 1) * 2, db1 + k * 128);
            wg_commit();
            wg_wait<1>();
            mbar_arrive_if(empty2 + w0 * 8, !isb && lane < 4);
            rel0 = w1;
            sl >>= 12; ph >>= 3;
        }
        wg_wait<0>();
        pin(acc);
        mbar_arrive_if(empty2 + so * 8, !isb && lane < 4);
        const uint32_t stg = sb + rel0 * STAGE;
        named_bar(1 + wg, 128);
        const uint32_t ra = stg + (warp * 16 + (lane & 15)) * 224 + (lane >> 4) * 16;
#pragma unroll
        for (int j = 0; j < 7; j++)
            stsm4(ra + j * 32, pack_bf16(acc[8 * j], acc[8 * j + 1]), pack_bf16(acc[8 * j + 2], acc[8 * j + 3]),
                  pack_bf16(acc[8 * j + 4], acc[8 * j + 5]), pack_bf16(acc[8 * j + 6], acc[8 * j + 7]));
        fence_async_smem();
        named_bar(1 + wg, 128);
        if ((tid & 127) == 0) {
            const int row = (cta >> 2) * 64;
            if (!isb)
                mbar_wait(full2 + ((int)(P.pslot[br * 2 + 1] >> 40) & 15) * 8, (P.pphase[br * 2 + 1] >> 10) & 1);
            asm volatile("cp.async.bulk.tensor.2d.global.shared::cta.bulk_group [%0, {%2, %3}], [%1];"
                         ::"l"(&P.out), "r"(stg), "r"(isb * 448 + (cta & 3) * 112), "r"(row) : "memory");
            bulk_commit();
            asm volatile("cp.async.bulk.wait_group.read 0;" ::: "memory");
        }
    }
}

typedef CUresult (*EncodeFn)(CUtensorMap*, CUtensorMapDataType, cuuint32_t, void*, const cuuint64_t*, const cuuint64_t*,
                             const cuuint32_t*, const cuuint32_t*, CUtensorMapInterleave, CUtensorMapSwizzle,
                             CUtensorMapL2promotion, CUtensorMapFloatOOBfill);

void make_map(EncodeFn enc, CUtensorMap* m, const void* ptr, uint64_t cols, uint64_t rows, uint32_t box_cols,
              uint32_t box_rows) {
    cuuint64_t dims[2] = {cols, rows};
    cuuint64_t strides[1] = {cols * 2};
    cuuint32_t box[2] = {box_cols, box_rows};
    cuuint32_t es[2] = {1, 1};
    enc(m, CU_TENSOR_MAP_DATA_TYPE_BFLOAT16, 2, const_cast<void*>(ptr), dims, strides, box, es,
        CU_TENSOR_MAP_INTERLEAVE_NONE, box_cols == 64 ? CU_TENSOR_MAP_SWIZZLE_128B : CU_TENSOR_MAP_SWIZZLE_NONE,
        CU_TENSOR_MAP_L2_PROMOTION_L2_128B, CU_TENSOR_MAP_FLOAT_OOB_FILL_NONE);
}

void make_wo_map(EncodeFn enc, CUtensorMap* m, const void* ptr) {
    cuuint64_t dims[5] = {112, 28, 2, 8, 4};
    cuuint64_t strides[4] = {DM * 2, 28 * DM * 2, 56 * DM * 2, 224};
    cuuint32_t box[5] = {64, 32, 1, 2, 1};
    cuuint32_t es[5] = {1, 1, 1, 1, 1};
    enc(m, CU_TENSOR_MAP_DATA_TYPE_BFLOAT16, 5, const_cast<void*>(ptr), dims, strides, box, es,
        CU_TENSOR_MAP_INTERLEAVE_NONE, CU_TENSOR_MAP_SWIZZLE_128B, CU_TENSOR_MAP_L2_PROMOTION_L2_128B,
        CU_TENSOR_MAP_FLOAT_OOB_FILL_NONE);
}

}

extern "C" void kernel_launch(void* const* d_in, const int* in_sizes, int n_in, void* d_out, int out_size) {
    static EncodeFn enc = nullptr;
    if (!enc) {
        void* fn = nullptr;
        cudaDriverEntryPointQueryResult qr;
        cudaGetDriverEntryPoint("cuTensorMapEncodeTiled", &fn, cudaEnableDefault, &qr);
        enc = reinterpret_cast<EncodeFn>(fn);
        cudaFuncSetAttribute(fused_kernel, cudaFuncAttributeMaxDynamicSharedMemorySize, SMEM_BYTES);
    }
    Params P;
    P.zero = 0;
    for (int i = 0; i < 4; i++) {
        P.pslot[i] = 0; P.pphase[i] = 0;
        for (int j = 0; j < 12; j++) {
            const int p = ((i >> 1) ? 22 : 25) + (i & 1) * 12 + j;
            P.pslot[i] |= (uint64_t)slot_of(i >> 1, p) << (4 * j);
            P.pphase[i] |= (uint32_t)((p / NST) & 1) << j;
        }
    }
    for (int i = 0; i < 16; i++) {
        const int z = i >> 3, wg = (i >> 1) & 3, task = i & 1;
        auto tiles = [&](int tk, int* t) {
            const int odd = (wg < 2) != tk, rt = odd ? 3 - wg : wg, n = z ? rt + 1 : 5;
            for (int k = 0; k < n; k++) { const int li = rt + 4 - k; t[k] = li >= 4 ? (odd ? 20 : -2) + li : (odd ? 10 : 6) + li; }
            return n;
        };
        auto qaddr = [&](int tk) { const int odd = (wg < 2) != tk; return 1024u + (odd ? 11 * STAGE + (3 - wg) * 4096 : wg * 4096); };
        int t[6], t1[6];
        const int n = tiles(task, t);
        tiles(1, t1);
        t[n] = task ? t[n - 1] : t1[0];
        uint32_t seq = 0;
        for (int k = 0; k <= n; k++) seq |= (uint32_t)t[k] << (5 * k);
        P.win[i] = make_uint4(qaddr(task), qaddr(1), seq, n);
    }
    for (int b = 0; b < 2; b++) {
        make_map(enc, &P.x[b], d_in[3 * b], DM, SEQ, 64, 256);
        P.w[b] = reinterpret_cast<const uint8_t*>(d_in[3 * b + 1]);
        make_wo_map(enc, &P.wo[b], d_in[3 * b + 2]);
    }
    P.wob = reinterpret_cast<const uint8_t*>(d_in[5]);
    make_map(enc, &P.out, d_out, 2 * DM, SEQ, 112, 64);
    cudaLaunchConfig_t cfg = {};
    cfg.gridDim = dim3(NCTA);
    cfg.blockDim = dim3(NTHR);
    cfg.dynamicSmemBytes = SMEM_BYTES;
    cfg.stream = cudaStreamPerThread;
    cudaLaunchAttribute at[1];
    at[0].id = cudaLaunchAttributeCooperative;
    at[0].val.cooperative = 1;
    cfg.attrs = at;
    cfg.numAttrs = 1;
    cudaLaunchKernelEx(&cfg, fused_kernel, P);
}
```
